```python
import torch

def _softmax(x, axis=-1):
    return torch.softmax(x, dim=axis)
def _gelu(x):
    return torch.nn.functional.gelu(x, approximate="tanh")
def _silu(x):
    return torch.nn.functional.silu(x)
def _sigmoid(x):
    return torch.sigmoid(x)
def _layernorm(x, axis=-1, eps=1e-5):
    m = x.mean(dim=axis, keepdim=True)
    v = x.var(dim=axis, keepdim=True, unbiased=False)
    return (x - m) / torch.sqrt(v + eps)
def _scatter_add(tgt, idx, src, axis=0):
    return tgt.clone().index_add_(axis, idx, src)
def _segment_sum(src, seg, n):
    out = torch.zeros((n,) + src.shape[1:], dtype=src.dtype)
    return out.index_add_(0, seg, src)
def _pad(x, pw):
    flat = tuple(v for pair in reversed(pw) for v in pair)
    return torch.nn.functional.pad(x, flat)

kernel_name = 'standalone__gqa_block_cached__sampling'

def setup_inputs():

    _w = (lambda a: (lambda t: t.to(torch.bfloat16) if t.is_floating_point() else t)(torch.as_tensor(a)))
    B, Sq, D = 16, 8, 512
    Hq, Hkv, Sk, Dh = 32, 8, 4096, 128
    assert Hq % Hkv == 0, (Hq, Hkv)
    return {
        "x": _w((lambda *s: torch.randn(*s, dtype=torch.bfloat16) * 0.8)(B, Sq, D)),
        "k_cache": _w((lambda *s: torch.randn(*s, dtype=torch.bfloat16) * 0.8)(B, Hkv, Sk, Dh)),
        "v_cache": _w((lambda *s: torch.randn(*s, dtype=torch.bfloat16) * 0.05)(B, Hkv, Sk, Dh)),
        "wq": _w((lambda *s: torch.randn(*s, dtype=torch.bfloat16) * 0.8)(D, Hq * Dh) * (D ** -0.5)),
        "wo": _w((lambda *s: torch.randn(*s, dtype=torch.bfloat16) * 0.05)(Hq * Dh, D) * ((Hq * Dh) ** -0.5)),
    }

def reference(x, k_cache, v_cache, wq, wo):
    B, Sq, D = x.shape
    Hq, Dh = 32, 128
    Hkv = k_cache.shape[1]
    rep = Hq // Hkv
    q = (lambda x, *d: x.permute(*d))((x @ wq).reshape(B, Sq, Hq, Dh), 0, 2, 1, 3)
    k = (lambda x, n, axis: torch.repeat_interleave(x, n, dim=axis))(k_cache, rep, axis=1)
    v = (lambda x, n, axis: torch.repeat_interleave(x, n, dim=axis))(v_cache, rep, axis=1)
    scores = torch.einsum("bhqd,bhkd->bhqk", q, k) * (Dh ** -0.5)
    p = _softmax(scores, axis=-1)
    o = torch.einsum("bhqk,bhkd->bhqd", p, v)
    return (lambda x, *d: x.permute(*d))(o, 0, 2, 1, 3).reshape(B, Sq, Hq * Dh) @ wo
```

```cpp
#include <cuda_runtime.h>
#include <cuda.h>
#include <cuda_bf16.h>
#include <stdint.h>

#define TILE 64
#define NSLOTS (TILE == 64 ? 9 : 4)
#define WIN 6
#define DMAX 8
#define D_PRO 3
#define N_PRO 8
#define WO_AT NT
#define WO_EARLY 2
#define WO_AT2 (NKV - 4)
#define RESET_SLEEP 300
#define T_RESET (NT / 4)
#define O_UPFRONT 24
#define WPROMO CU_TENSOR_MAP_L2_PROMOTION_L2_128B
#define RS_STEPS 28
#define PREFETCH_MAPS 1
#define N_FIRST D_PRO
#define Q_SLEEP 1400

namespace {

constexpr int kSk = 4096;
constexpr int T = TILE;
constexpr int MB = T / 64;
constexpr int SLOT = T * 256;
constexpr int NS = NSLOTS;
constexpr int XCH = 2 * T;
constexpr int NX = 512 / XCH;
constexpr int NT = kSk / T;
constexpr int NKV = 2 * NT;

constexpr int OB_SLOTS = 65536 / SLOT;
constexpr int START = (2 * NS - 1 - (NX + NKV - 1) % NS) % NS;
constexpr int T_OBUF = (NKV - 1 - (NS - OB_SLOTS)) / 2 + 1;
static_assert(START + NX <= NS, "x must not wrap around the ring");

constexpr int OFF_W = NS * SLOT;
constexpr int OFF_Q = OFF_W + 65536;
constexpr int OFF_P = OFF_Q + 8192;
constexpr int P_BYTES = T * 64;
constexpr int OFF_RED = OFF_P + 2 * P_BYTES;
constexpr int OFF_BAR = OFF_RED + 1024;
constexpr int OFF_TS = OFF_BAR + 256;
constexpr int SMEM_BYTES = OFF_TS;
static_assert(2 * NS + 10 <= 29 && N_FIRST <= NS - NX && DMAX <= NS && 2 * P_BYTES >= 8192 && SMEM_BYTES <= 232448, "shared memory layout");

constexpr uint32_t kEmpty = 0xFFFFFFFFu;
constexpr int kSpinLimit = 1 << 24;

__device__ uint4 g_xq[128 * 512];
__device__ uint4 g_xo[128 * 512];
__device__ uint4 g_xp[128 * 1024];
__device__ unsigned g_hint[128 * 32];
__device__ unsigned g_ctr[3 * 32];

#define STAMP(i)
#define STAMP_ME(i)
#define STAMP_FLUSH()
#define STAMP_INIT()

__device__ __forceinline__ uint32_t smem_u32(const void* p) { return (uint32_t)__cvta_generic_to_shared(p); }

__device__ __forceinline__ void mbar_init(uint32_t bar, uint32_t cnt) {
    asm volatile("mbarrier.init.shared::cta.b64 [%0], %1;" ::"r"(bar), "r"(cnt) : "memory");
}
__device__ __forceinline__ void mbar_expect_tx(uint32_t bar, uint32_t bytes) {
    asm volatile("mbarrier.arrive.expect_tx.shared::cta.b64 _, [%0], %1;" ::"r"(bar), "r"(bytes) : "memory");
}
__device__ __forceinline__ void mbar_arrive(uint32_t bar) {
    asm volatile("mbarrier.arrive.shared::cta.b64 _, [%0];" ::"r"(bar) : "memory");
}
__device__ __forceinline__ void mbar_wait(uint32_t bar, uint32_t parity) {
    uint32_t ok;
    int it = 0;
    do {
        asm volatile(
            "{\n.reg .pred p;\n"
            "mbarrier.try_wait.parity.shared::cta.b64 p, [%1], %2;\n"
            "selp.u32 %0, 1, 0, p;\n}"
            : "=r"(ok) : "r"(bar), "r"(parity) : "memory");
        if (++it > kSpinLimit) __trap();
    } while (!ok);
}
__device__ __forceinline__ bool mbar_test(uint32_t bar, uint32_t parity) {
    uint32_t ok;
    asm volatile(
        "{\n.reg .pred p;\n"
        "mbarrier.test_wait.parity.shared::cta.b64 p, [%1], %2;\n"
        "selp.u32 %0, 1, 0, p;\n}"
        : "=r"(ok) : "r"(bar), "r"(parity) : "memory");
    return ok != 0;
}
__device__ __forceinline__ void wg_bar() { asm volatile("bar.sync 1, 128;" ::: "memory"); }
__device__ __forceinline__ void fence_async_smem() { asm volatile("fence.proxy.async.shared::cta;" ::: "memory"); }

__device__ __forceinline__ void tma_2d(uint32_t dst, const CUtensorMap* m, uint32_t bar, int c0, int c1) {
    asm volatile("cp.async.bulk.tensor.2d.shared::cluster.global.mbarrier::complete_tx::bytes [%0], [%1, {%3, %4}], [%2];"
                 ::"r"(dst), "l"(m), "r"(bar), "r"(c0), "r"(c1) : "memory");
}
__device__ __forceinline__ void tma_3d(uint32_t dst, const CUtensorMap* m, uint32_t bar, int c0, int c1, int c2) {
    asm volatile("cp.async.bulk.tensor.3d.shared::cluster.global.mbarrier::complete_tx::bytes [%0], [%1, {%3, %4, %5}], [%2];"
                 ::"r"(dst), "l"(m), "r"(bar), "r"(c0), "r"(c1), "r"(c2) : "memory");
}
__device__ __forceinline__ void tma_kv(uint32_t dst, const CUtensorMap* m, uint32_t bar, int group, uint64_t pol) {
    asm volatile("cp.async.bulk.tensor.4d.shared::cluster.global.mbarrier::complete_tx::bytes.L2::cache_hint "
                 "[%0], [%1, {%3, %3, %3, %4}], [%2], %5;"
                 ::"r"(dst), "l"(m), "r"(bar), "r"(0), "r"(group), "l"(pol) : "memory");
}

__device__ __forceinline__ void bulk_load(uint32_t dst, const void* src, uint32_t bytes, uint32_t bar) {
    asm volatile("cp.async.bulk.shared::cluster.global.mbarrier::complete_tx::bytes [%0], [%1], %2, [%3];"
                 ::"r"(dst), "l"(src), "r"(bytes), "r"(bar) : "memory");
}

__device__ __forceinline__ uint32_t desc_lo(uint32_t addr) { return ((addr & 0x3FFFF) >> 4) | (1u << 16); }
__host__ __device__ constexpr uint32_t desc_hi(uint32_t sbo) { return (sbo >> 4) | (1u << 30); }
__device__ __forceinline__ void wg_fence() { asm volatile("wgmma.fence.sync.aligned;" ::: "memory"); }
__device__ __forceinline__ void wg_commit() { asm volatile("wgmma.commit_group.sync.aligned;" ::: "memory"); }
__device__ __forceinline__ void wg_wait0() { asm volatile("wgmma.wait_group.sync.aligned 0;" ::: "memory"); }

template <int N>
__device__ __forceinline__ void pin(float (&d)[N]) {
#pragma unroll
    for (int i = 0; i < N; i++) asm volatile("" : "+f"(d[i])::"memory");
}

template <int TA, int SBO_A = 2048, int SBO_B = 1024>
__device__ __forceinline__ void mma_n32_ss(float (&d)[16], uint32_t a, uint32_t b, int acc) {
    asm volatile(
        "{\n.reg .pred p;\n.reg .b64 da, db;\nsetp.ne.b32 p, %18, 0;\n"
        "mov.b64 da, {%16, %20};\nmov.b64 db, {%17, %21};\n"
        "wgmma.mma_async.sync.aligned.m64n32k16.f32.bf16.bf16 "
        "{%0,%1,%2,%3,%4,%5,%6,%7,%8,%9,%10,%11,%12,%13,%14,%15}, da, db, p, 1, 1, %19, 0;\n}"
        : "+f"(d[0]), "+f"(d[1]), "+f"(d[2]), "+f"(d[3]), "+f"(d[4]), "+f"(d[5]), "+f"(d[6]), "+f"(d[7]),
          "+f"(d[8]), "+f"(d[9]), "+f"(d[10]), "+f"(d[11]), "+f"(d[12]), "+f"(d[13]), "+f"(d[14]), "+f"(d[15])
        : "r"(a), "r"(b), "r"(acc), "n"(TA), "n"(desc_hi(SBO_A)), "n"(desc_hi(SBO_B)));
}
__device__ __forceinline__ void mma_n32_rs(float (&d)[16], const uint32_t (&a)[4], uint32_t b, int acc) {
    asm volatile(
        "{\n.reg .pred p;\n.reg .b64 db;\nsetp.ne.b32 p, %21, 0;\n"
        "mov.b64 db, {%20, %22};\n"
        "wgmma.mma_async.sync.aligned.m64n32k16.f32.bf16.bf16 "
        "{%0,%1,%2,%3,%4,%5,%6,%7,%8,%9,%10,%11,%12,%13,%14,%15}, {%16,%17,%18,%19}, db, p, 1, 1, 0;\n}"
        : "+f"(d[0]), "+f"(d[1]), "+f"(d[2]), "+f"(d[3]), "+f"(d[4]), "+f"(d[5]), "+f"(d[6]), "+f"(d[7]),
          "+f"(d[8]), "+f"(d[9]), "+f"(d[10]), "+f"(d[11]), "+f"(d[12]), "+f"(d[13]), "+f"(d[14]), "+f"(d[15])
        : "r"(a[0]), "r"(a[1]), "r"(a[2]), "r"(a[3]), "r"(b), "r"(acc), "n"(desc_hi(8192)));
}
#define ACC32_REGS "{%0,%1,%2,%3,%4,%5,%6,%7,%8,%9,%10,%11,%12,%13,%14,%15,%16,%17,%18,%19,%20,%21,%22,%23,%24,%25,%26,%27,%28,%29,%30,%31}"
#define ACC32_OPS(d)                                                                                              \
    "+f"(d[0]), "+f"(d[1]), "+f"(d[2]), "+f"(d[3]), "+f"(d[4]), "+f"(d[5]), "+f"(d[6]), "+f"(d[7]), "+f"(d[8]),   \
        "+f"(d[9]), "+f"(d[10]), "+f"(d[11]), "+f"(d[12]), "+f"(d[13]), "+f"(d[14]), "+f"(d[15]), "+f"(d[16]),    \
        "+f"(d[17]), "+f"(d[18]), "+f"(d[19]), "+f"(d[20]), "+f"(d[21]), "+f"(d[22]), "+f"(d[23]), "+f"(d[24]),   \
        "+f"(d[25]), "+f"(d[26]), "+f"(d[27]), "+f"(d[28]), "+f"(d[29]), "+f"(d[30]), "+f"(d[31])
__device__ __forceinline__ void mma_n64_ss(float (&d)[32], uint32_t a, uint32_t b, int acc) {
    asm volatile(
        "{\n.reg .pred p;\n.reg .b64 da, db;\nsetp.ne.b32 p, %34, 0;\n"
        "mov.b64 da, {%32, %35};\nmov.b64 db, {%33, %35};\n"
        "wgmma.mma_async.sync.aligned.m64n64k16.f32.bf16.bf16 " ACC32_REGS ", da, db, p, 1, 1, 0, 1;\n}"
        : ACC32_OPS(d) : "r"(a), "r"(b), "r"(acc), "n"(desc_hi(1024)));
}
__device__ __forceinline__ uint32_t pack_bf16(float lo, float hi) {
    uint32_t r;
    asm("cvt.rn.bf16x2.f32 %0, %1, %2;" : "=r"(r) : "f"(hi), "f"(lo));
    return r;
}
__device__ __forceinline__ float ex2(float x) {
    float r;
    asm("ex2.approx.ftz.f32 %0, %1;" : "=f"(r) : "f"(x));
    return r;
}
__device__ __forceinline__ float rcp(float x) {
    float r;
    asm("rcp.approx.ftz.f32 %0, %1;" : "=f"(r) : "f"(x));
    return r;
}
__device__ __forceinline__ uint32_t transpose8x8(uint32_t a) {
    uint32_t d;
    asm volatile("movmatrix.sync.aligned.m8n8.trans.b16 %0, %1;" : "=r"(d) : "r"(a));
    return d;
}
__device__ __forceinline__ void st_gpu(uint4* p, uint4 v) {
    asm volatile("st.relaxed.gpu.global.v4.u32 [%0], {%1,%2,%3,%4};" ::"l"(p), "r"(v.x), "r"(v.y), "r"(v.z), "r"(v.w) : "memory");
}
__device__ __forceinline__ uint4 ld_gpu(const uint4* p) {
    uint4 v;
    asm volatile("ld.relaxed.gpu.global.v4.u32 {%0,%1,%2,%3}, [%4];" : "=r"(v.x), "=r"(v.y), "=r"(v.z), "=r"(v.w) : "l"(p) : "memory");
    return v;
}
__device__ __forceinline__ void st_gpu(uint32_t* p, uint32_t v) {
    asm volatile("st.relaxed.gpu.global.u32 [%0], %1;" ::"l"(p), "r"(v) : "memory");
}
__device__ __forceinline__ uint32_t ld_gpu(const uint32_t* p) {
    uint32_t v;
    asm volatile("ld.relaxed.gpu.global.u32 %0, [%1];" : "=r"(v) : "l"(p) : "memory");
    return v;
}
__device__ __forceinline__ bool has_empty(uint4 v) { return v.x == kEmpty || v.y == kEmpty || v.z == kEmpty || v.w == kEmpty; }
__device__ __forceinline__ void fence_gpu() { asm volatile("fence.acq_rel.gpu;" ::: "memory"); }
template <unsigned N>
__device__ __forceinline__ void counter_barrier(unsigned* ctr, unsigned seen_before_arrival) {
    const unsigned target = (seen_before_arrival & ~(N - 1)) + N;
    fence_gpu();
    asm volatile("red.relaxed.gpu.global.add.u32 [%0], 1;" ::"l"(ctr) : "memory");
    int it = 0;
    while ((int)(ld_gpu(ctr) - target) < 0)
        if (++it > kSpinLimit) __trap();
    fence_gpu();
}
__device__ __forceinline__ bool wg_any(bool v) {
    uint32_t r;
    asm volatile("{\n.reg .pred p, q;\nsetp.ne.u32 p, %1, 0;\nbar.red.or.pred q, 2, 128, p;\nselp.u32 %0, 1, 0, q;\n}"
                 : "=r"(r) : "r"((uint32_t)v) : "memory");
    return r != 0;
}

template <bool IS_MAX>
__device__ __forceinline__ float reduce_scatter8(const float (&v)[8], int lane) {
    auto op = [](float a, float b) { return IS_MAX ? fmaxf(a, b) : a + b; };
    const bool b4 = lane & 16, b3 = lane & 8, b2 = lane & 4;
    float a[4], c[2];
#pragma unroll
    for (int i = 0; i < 4; i++) a[i] = op(b4 ? v[i + 4] : v[i], __shfl_xor_sync(~0u, b4 ? v[i] : v[i + 4], 16));
#pragma unroll
    for (int i = 0; i < 2; i++) c[i] = op(b3 ? a[i + 2] : a[i], __shfl_xor_sync(~0u, b3 ? a[i] : a[i + 2], 8));
    return op(b2 ? c[1] : c[0], __shfl_xor_sync(~0u, b2 ? c[0] : c[1], 4));
}

__device__ __forceinline__ uint32_t uniform(uint32_t v) { return __shfl_sync(~0u, v, 0); }

__device__ __forceinline__ bool kv_is_k(int i) { return i == 0 || ((i & 1) && i != NKV - 1); }
__device__ __forceinline__ int kv_tile(int i) { return kv_is_k(i) ? (i + 1) >> 1 : (i - 1) >> 1; }

struct Cursor {
    int slot = START, phase = 0;
    __device__ __forceinline__ void next() {
        if (++slot == NS) { slot = 0; phase ^= 1; }
    }
};

__global__ void __launch_bounds__(384, 1)
gqa_fused_kernel(const __grid_constant__ CUtensorMap map_x, const __grid_constant__ CUtensorMap map_wq,
                 const __grid_constant__ CUtensorMap map_k, const __grid_constant__ CUtensorMap map_v,
                 const __grid_constant__ CUtensorMap map_wo, __nv_bfloat16* __restrict__ out) {
    extern __shared__ __align__(1024) uint8_t smem[];
    const uint32_t sbase = smem_u32(smem);
    const uint32_t bar_full = sbase + OFF_BAR, bar_empty = bar_full + NS * 8;
    const uint32_t bar_reset_go = bar_empty + NS * 8, bar_reset_done = bar_reset_go + 8;
    const uint32_t bar_w_empty = bar_reset_done + 8, bar_w = bar_w_empty + 8;
    const uint32_t bar_obuf = bar_w + 32, bar_o = bar_obuf + 8;
    volatile uint8_t* o_order = smem + OFF_BAR + 240;
    unsigned* o_count = reinterpret_cast<unsigned*>(smem + OFF_BAR + 232);

    volatile int* mean_landed = reinterpret_cast<volatile int*>(smem + OFF_BAR + 248);
    const int tid = threadIdx.x, warp = tid >> 5, lane = tid & 31;
    const int cta = blockIdx.x, b = cta >> 3, g = cta & 7, mh = b >> 3, jl = b & 7;
    STAMP_INIT();
    STAMP(0);

    uint64_t pol = 0;
    if (tid == 128) {
        if (sbase & 1023) __trap();
#pragma unroll
        for (int i = 0; i < 4; i++) mbar_init(bar_w + i * 8, 1);
#pragma unroll
        for (int i = 0; i < NS; i++) mbar_init(bar_full + i * 8, 1);
        fence_async_smem();
#pragma unroll
        for (int c = 0; c < 4; c++) {
            mbar_expect_tx(bar_w + c * 8, 16384);
            tma_2d(sbase + OFF_W + c * 16384, &map_wq, bar_w + c * 8, (g * 8 + jl) * 64, c * 128);
            if (c % (4 / NX) == 0) {
                const int slot = START + c / (4 / NX);
                mbar_expect_tx(bar_full + slot * 8, SLOT);
                tma_3d(sbase + slot * SLOT, &map_x, bar_full + slot * 8, 0, mh * 64, c * 2);
            }
        }
#pragma unroll
        for (int i = 0; i < START; i++) mbar_arrive(bar_full + i * 8);
        asm volatile("createpolicy.fractional.L2::evict_first.b64 %0, 1.0;" : "=l"(pol));
#pragma unroll
        for (int i = 0; i < N_FIRST; i++) {
            const int slot = (START + NX + i) % NS;
            mbar_expect_tx(bar_full + slot * 8, SLOT);
            tma_kv(sbase + slot * SLOT, kv_is_k(i) ? &map_k : &map_v, bar_full + slot * 8, (cta * kSk + kv_tile(i) * T) >> 3, pol);
        }
#pragma unroll
        for (int i = 0; i < NS; i++) mbar_init(bar_empty + i * 8, 4);
        mbar_init(bar_reset_go, 1);
        mbar_init(bar_reset_done, 1);
        mbar_init(bar_w_empty, 4);
        mbar_init(bar_obuf, 4);
        mbar_init(bar_o, 4);
        mbar_init(bar_o + 8, 4);
#pragma unroll
        for (int i = 0; i < 4 * START; i++) mbar_arrive(bar_empty + (i >> 2) * 8);
        *mean_landed = 0;
        *o_count = 0;
        fence_async_smem();
    } else if (PREFETCH_MAPS && warp == 5 && lane < 4) {
        const CUtensorMap* m = lane == 0 ? &map_x : lane == 1 ? &map_k : lane == 2 ? &map_v : &map_wq;
        asm volatile("prefetch.tensormap [%0];" ::"l"(m) : "memory");
    }
    __syncthreads();

    if (warp >= 4) {
        if (warp == 4 && lane == 0) {
            Cursor cur;
#pragma unroll
            for (int i = 0; i < NX; i++) cur.next();
            Cursor lag = cur;
#pragma unroll
            for (int i = 0; i < N_FIRST; i++) cur.next();
            unsigned* progress = &g_ctr[64];
            int issued = N_FIRST, landed = 0, it = 0;
            int wo_issued = 0;
            while (landed < NKV || wo_issued < 4) {
                if (landed < issued && mbar_test(bar_full + lag.slot * 8, lag.phase)) {
                    asm volatile("red.relaxed.gpu.global.add.u32 [%0], 1;" ::"l"(progress) : "memory");
                    lag.next();
                    landed++;
                    it = 0;
                    if (landed > NKV - 6) STAMP_ME(21 + landed - (NKV - 5));
                } else if (issued < NKV && issued - landed < (issued < N_PRO ? D_PRO : DMAX) &&
                           (issued < *mean_landed + WIN || issued == landed) &&
                           mbar_test(bar_empty + cur.slot * 8, cur.phase ^ 1)) {
                    mbar_expect_tx(bar_full + cur.slot * 8, SLOT);
                    tma_kv(sbase + cur.slot * SLOT, kv_is_k(issued) ? &map_k : &map_v, bar_full + cur.slot * 8,
                           (cta * kSk + kv_tile(issued) * T) >> 3, pol);
                    cur.next();
                    issued++;
                } else if (wo_issued < 4 && *mean_landed >= (wo_issued < WO_EARLY ? WO_AT : WO_AT2) && mbar_test(bar_w_empty, 0)) {
                    mbar_expect_tx(bar_w + wo_issued * 8, 16384);
                    tma_2d(sbase + OFF_W + wo_issued * 16384, &map_wo, bar_w + wo_issued * 8, jl * 64, g * 512 + wo_issued * 128);
                    wo_issued++;
                } else if (++it > kSpinLimit) {
                    __trap();
                }
            }
        } else if (warp == 5) {
            unsigned* ctr = &g_ctr[mh * 32];
            unsigned seen = 0;
            if (lane == 0) seen = ld_gpu(ctr);
            mbar_wait(bar_reset_go, 0);
            const uint4 e = make_uint4(kEmpty, kEmpty, kEmpty, kEmpty);
#pragma unroll 1
            for (int i = 0; i < 16; i++) {
                st_gpu(&g_xo[cta * 512 + i * 32 + lane], e);
                __nanosleep(RESET_SLEEP);
                st_gpu(&g_xp[cta * 1024 + i * 64 + lane], e);
                __nanosleep(RESET_SLEEP);
                st_gpu(&g_xp[cta * 1024 + i * 64 + 32 + lane], e);
                __nanosleep(RESET_SLEEP);
                st_gpu(&g_xq[cta * 512 + i * 32 + lane], make_uint4(0, 0, 0, 0));
                __nanosleep(RESET_SLEEP);
            }
            __syncwarp();
            if (lane == 0) {
                st_gpu(&g_hint[cta * 32], 0u);
                counter_barrier<64>(ctr, seen);
                mbar_arrive(bar_reset_done);
            }
        } else if (warp == 6) {
            if (lane == 0) {
                const unsigned total = 128 * NKV;
                const unsigned base = ld_gpu(&g_ctr[64]) & ~(total - 1);
                unsigned done;
                int it = 0;
                do {
                    done = ld_gpu(&g_ctr[64]) - base;
                    *mean_landed = done >> 7;
                    if (++it > kSpinLimit) __trap();
                } while (done < 128 * (WO_EARLY < 4 && WO_AT2 > NKV - WIN ? WO_AT2 : NKV - WIN));
            }
        }
        __syncwarp();
        mbar_wait(bar_reset_done, 0);
        mbar_wait(bar_obuf, 0);
        asm volatile("fence.proxy.async.global;" ::: "memory");
        if (lane == 0) {
            const int lb = (jl + warp - 4) & 7, src_cta = (mh * 8 + lb) * 8 + g;
            const uint4* src = &g_xo[src_cta * 512];
            int it = 0;
            while (ld_gpu(&g_hint[src_cta * 32]) < 4u)
                if (++it > kSpinLimit) __trap();
            unsigned slot;
            asm volatile("atom.relaxed.cta.shared.add.u32 %0, [%1], 1;" : "=r"(slot) : "r"(sbase + OFF_BAR + 232) : "memory");
            o_order[slot] = lb;
            mbar_expect_tx(bar_o + (slot >> 2) * 8, 8192);
            bulk_load(sbase + slot * 8192, src, 8192, bar_o + (slot >> 2) * 8);
            if (slot == 7) STAMP_ME(19);
            if (slot == 3) STAMP_ME(18);
        }
    } else {

    const int g8 = lane >> 2, t4 = lane & 3;
    Cursor cur;
    const uint32_t ring_lo = desc_lo(sbase), w_lo = desc_lo(sbase + OFF_W);

    {
        float acc[32];
#pragma unroll
        for (int c = 0; c < 4; c++) {
            mbar_wait(bar_w + c * 8, 0);
            if (c % (4 / NX) == 0) mbar_wait(bar_full + (START + c / (4 / NX)) * 8, 0);
            wg_fence();
#pragma unroll
            for (int ks = 0; ks < 8; ks++)
                mma_n64_ss(acc, ring_lo + START * (SLOT / 16) + (2 * c + (ks >> 2)) * 512 + (ks & 3) * 2, w_lo + (8 * c + ks) * 128, (c | ks) != 0);
            wg_commit();
        }
        STAMP(1);
        wg_wait0();
        pin(acc);
        if (lane == 0) mbar_arrive(bar_w_empty);
#pragma unroll
        for (int i = 0; i < NX; i++) {
            if (lane == 0) mbar_arrive(bar_empty + (START + i) * 8);
            cur.next();
        }
        STAMP(2);
        uint32_t* stage = reinterpret_cast<uint32_t*>(smem + OFF_P);
#pragma unroll
        for (int j = 0; j < 8; j++) {
#pragma unroll
            for (int hi = 0; hi < 2; hi++)
                stage[(2 * warp + hi) * 256 + g8 * 32 + ((j ^ g8) << 2) + t4] = ~pack_bf16(acc[4 * j + 2 * hi], acc[4 * j + 2 * hi + 1]);
        }
        wg_bar();
#pragma unroll
        for (int i = 0; i < 4; i++) {
            const int u = i * 128 + tid, lb = u >> 6;
            const uint4 v = reinterpret_cast<const uint4*>(stage)[u];
            st_gpu(&g_xq[((mh * 8 + lb) * 8 + g) * 512 + (jl & 1) * 256 + (jl >> 1) * 64 + (u & 63)], v);
        }
        STAMP(3);
        __nanosleep(Q_SLEEP);
        uint4* inbox = &g_xq[cta * 512 + tid];
        uint4 v[4];
        int it = 0;
        bool missing;
        do {
            missing = false;
#pragma unroll
            for (int i = 0; i < 4; i++) v[i] = ld_gpu(inbox + i * 128);
#pragma unroll
            for (int i = 0; i < 4; i++) missing |= v[i].x == 0 || v[i].y == 0 || v[i].z == 0 || v[i].w == 0;
            if (++it > kSpinLimit) __trap();
        } while (missing);
#pragma unroll
        for (int i = 0; i < 4; i++)
            reinterpret_cast<uint4*>(smem + OFF_Q)[i * 128 + tid] = make_uint4(~v[i].x, ~v[i].y, ~v[i].z, ~v[i].w);
        fence_async_smem();
        wg_bar();
        STAMP(4);
    }

    const float kScale = 0.08838834764831845f * 1.4426950408889634f;
    float o[2][16], mc[8], l_run[8];
#pragma unroll
    for (int i = 0; i < 16; i++) o[0][i] = o[1][i] = 0.f;
#pragma unroll
    for (int i = 0; i < 8; i++) { mc[i] = -INFINITY; l_run[i] = 0.f; }
    float* red = reinterpret_cast<float*>(smem + OFF_RED);
    const int red_wr = (8 * (g8 >> 1) + 2 * t4 + (g8 & 1)) * 4 + warp;
    const uint32_t q_lo = desc_lo(sbase + OFF_Q), p_lo = desc_lo(sbase + OFF_P);
    const uint32_t p_st = sbase + OFF_P + ((lane >> 4) * 8 + (lane & 7)) * 128 + (((2 * warp + ((lane >> 3) & 1)) ^ (lane & 7)) << 4);
    float inv_l[8];

#pragma unroll 1
    for (int t = 0; t <= NT; t++) {
        float s[MB][16], alpha[8];
        if (t < NT) {
            const uint32_t k_lo = uniform(ring_lo + cur.slot * (SLOT / 16));
            mbar_wait(bar_full + cur.slot * 8, cur.phase);
            if (t == NT - 1) STAMP(5);
            STAMP(32 + t);
            wg_fence();
#pragma unroll
            for (int mb = 0; mb < MB; mb++) {
#pragma unroll
                for (int ks = 0; ks < 8; ks++)
                    mma_n32_ss<0>(s[mb], k_lo + mb * 1024 + (ks >> 2) * 64 + (ks & 3) * 2, q_lo + (ks >> 2) * 256 + (ks & 3) * 2, ks != 0);
            }
            wg_commit();
            wg_wait0();
#pragma unroll
            for (int mb = 0; mb < MB; mb++) pin(s[mb]);
            if (lane == 0) mbar_arrive(bar_empty + cur.slot * 8);
            cur.next();
            float mx[8];
#pragma unroll
            for (int i = 0; i < 8; i++) {
                const int r = (i >> 1) * 4 + (i & 1);
                mx[i] = fmaxf(s[0][r], s[0][r + 2]);
#pragma unroll
                for (int mb = 1; mb < MB; mb++) mx[i] = fmaxf(mx[i], fmaxf(s[mb][r], s[mb][r + 2]));
            }
            red[red_wr] = reduce_scatter8<true>(mx, lane);
            wg_bar();
#pragma unroll
            for (int i = 0; i < 8; i++) {
                const float4 v = reinterpret_cast<const float4*>(red)[8 * (i >> 1) + 2 * t4 + (i & 1)];
                const float m_new = fmaxf(mc[i], fmaxf(fmaxf(v.x, v.y), fmaxf(v.z, v.w)) * kScale);
                alpha[i] = ex2(mc[i] - m_new);
                mc[i] = m_new;
                l_run[i] *= alpha[i];
            }
        } else {
#pragma unroll
            for (int i = 0; i < 8; i++) {
                const float4 v = reinterpret_cast<const float4*>(red + 128)[8 * (i >> 1) + 2 * t4 + (i & 1)];
                inv_l[i] = rcp((v.x + v.y) + (v.z + v.w));
            }
        }
        const int v_slot = cur.slot;
        if (t > 0) {
            const uint32_t v_lo = uniform(ring_lo + cur.slot * (SLOT / 16)), pb = uniform(p_lo + ((t - 1) & 1) * (P_BYTES / 16));
            mbar_wait(bar_full + cur.slot * 8, cur.phase);
            if (t == NT) STAMP(6);
            STAMP(96 + t - 1);
            wg_fence();
#pragma unroll
            for (int ks = 0; ks < T / 16; ks++) {
#pragma unroll
                for (int mb = 0; mb < 2; mb++)
                    mma_n32_ss<1>(o[mb], v_lo + ks * 256 + mb * 64, pb + (ks >> 2) * 256 + (ks & 3) * 2, 1);
            }
            wg_commit();
            cur.next();
        }
        if (t < NT) {
#pragma unroll
            for (int mb = 0; mb < MB; mb++) {
                uint32_t pk[8];
#pragma unroll
                for (int j = 0; j < 4; j++) {
#pragma unroll
                    for (int hi = 0; hi < 2; hi++) {
                        const float p0 = ex2(fmaf(s[mb][4 * j + 2 * hi], kScale, -mc[2 * j]));
                        const float p1 = ex2(fmaf(s[mb][4 * j + 2 * hi + 1], kScale, -mc[2 * j + 1]));
                        l_run[2 * j] += p0;
                        l_run[2 * j + 1] += p1;
                        pk[2 * j + hi] = pack_bf16(p0, p1);
                    }
                }
#pragma unroll
                for (int jp = 0; jp < 2; jp++)
                    asm volatile("stmatrix.sync.aligned.m8n8.x4.trans.shared.b16 [%0], {%1,%2,%3,%4};"
                                 ::"r"(p_st + (t & 1) * P_BYTES + mb * 4096 + jp * 2048), "r"(pk[4 * jp]), "r"(pk[4 * jp + 1]),
                                   "r"(pk[4 * jp + 2]), "r"(pk[4 * jp + 3])
                                 : "memory");
            }
            if (t == NT - 1) red[128 + red_wr] = reduce_scatter8<false>(l_run, lane);
            fence_async_smem();
        }
        wg_wait0();
        pin(o[0]);
        pin(o[1]);
        if (t > 0 && lane == 0) mbar_arrive(bar_empty + v_slot * 8);
        if (t == T_OBUF && lane == 0) mbar_arrive(bar_obuf);
        if (t < NT) {
#pragma unroll
            for (int mb = 0; mb < 2; mb++) {
#pragma unroll
                for (int i = 0; i < 16; i++) o[mb][i] *= alpha[(i >> 2) * 2 + (i & 1)];
            }
            wg_bar();
            if (t == T_RESET && tid == 0) mbar_arrive(bar_reset_go);
            if (t == NT - 2) mbar_wait(bar_reset_done, 0);
            STAMP(160 + t);
        }
    }
    STAMP(7);

    {
        const uint32_t st = sbase + OFF_Q + warp * 2048 + (lane & 7) * 128;
#pragma unroll
        for (int r = 0; r < 4; r++) {
            uint32_t pk[4];
#pragma unroll
            for (int i = 0; i < 4; i++)
                pk[i] = pack_bf16(o[i >> 1][4 * r + 2 * (i & 1)] * inv_l[2 * r], o[i >> 1][4 * r + 2 * (i & 1) + 1] * inv_l[2 * r + 1]);
            asm volatile("stmatrix.sync.aligned.m8n8.x4.trans.shared.b16 [%0], {%1,%2,%3,%4};"
                         ::"r"(st + (r >> 1) * 1024 + ((((r & 1) * 4 + (lane >> 3)) ^ (lane & 7)) << 4)),
                           "r"(pk[0]), "r"(pk[1]), "r"(pk[2]), "r"(pk[3]) : "memory");
        }
        __syncwarp();
#pragma unroll
        for (int i = 0; i < 4; i++)
            st_gpu(&g_xo[cta * 512 + warp * 128 + i * 32 + lane], reinterpret_cast<const uint4*>(smem + OFF_Q)[warp * 128 + i * 32 + lane]);
    }
    if (lane == 0) asm volatile("red.relaxed.gpu.global.add.u32 [%0], 1;" ::"l"(&g_hint[cta * 32]) : "memory");
    STAMP(8);

    uint32_t wf[RS_STEPS][4];
    {
        const uint32_t wa = sbase + OFF_W + ((lane >> 4) * 8 + (lane & 7)) * 128 + (((2 * warp + ((lane >> 3) & 1)) ^ (lane & 7)) << 4);
#pragma unroll
        for (int ks = 0; ks < 32; ks++) {
            if (ks % 8 == 0) mbar_wait(bar_w + (ks / 8) * 8, 1);
            const int step = 8 * (ks & 3) + (ks >> 2);
            if (step < RS_STEPS)
                asm volatile("ldmatrix.sync.aligned.m8n8.x4.trans.shared.b16 {%0,%1,%2,%3}, [%4];"
                         : "=r"(wf[step][0]), "=r"(wf[step][1]), "=r"(wf[step][2]), "=r"(wf[step][3]) : "r"(wa + ks * 2048) : "memory");
        }
    }
    STAMP(9);
    bool suspect_any = false;
#pragma unroll 1
    for (int pass = 0;; pass++) {
        const int quad = pass & 1;
        const uint32_t ob = uniform(ring_lo + quad * 2048);
        mbar_wait(bar_o + quad * 8, (pass >> 1) & 1);
        const uint32_t order = *reinterpret_cast<const volatile uint32_t*>(o_order + quad * 4);
        STAMP(10 + 5 * quad);
        float acc[16];
        wg_fence();
#pragma unroll
        for (int ks = 0; ks < 32; ks++) {
            const uint32_t bd = ob + (ks >> 2) * 64 + (ks & 3) * 2;
            if (ks < RS_STEPS) mma_n32_rs(acc, wf[ks], bd, ks != 0);
            else mma_n32_ss<1, 1024, 8192>(acc, w_lo + (4 * (ks & 7) + (ks >> 3)) * 128, bd, 1);
        }
        wg_commit();
        wg_wait0();
        pin(acc);
        STAMP(11 + 5 * quad);
        float any = 0.f;
#pragma unroll
        for (int j = 0; j < 4; j++) any += acc[4 * j] + acc[4 * j + 1];
        bool suspect = any != any;
        if (__any_sync(~0u, suspect)) {
            bool hole = false;
#pragma unroll 1
            for (int i = lane; i < 2048; i += 32) hole |= has_empty(reinterpret_cast<const uint4*>(smem)[quad * 2048 + i]);
            suspect &= __any_sync(~0u, hole);
        }
        if (!suspect) {
#pragma unroll
            for (int j = 0; j < 4; j++)
                st_gpu(&g_xp[(b * 8 + ((order >> (8 * j)) & 7)) * 1024 + g * 128 + tid],
                       make_uint4(__float_as_uint(acc[4 * j]), __float_as_uint(acc[4 * j + 1]),
                                  __float_as_uint(acc[4 * j + 2]), __float_as_uint(acc[4 * j + 3])));
        }
        suspect_any |= suspect;
        STAMP(12 + 5 * quad);
        if (quad == 1) {
            if (!wg_any(suspect_any)) break;
            if (pass > kSpinLimit) __trap();
            suspect_any = false;
            if (tid < 8) {
                fence_async_smem();
                mbar_expect_tx(bar_o + (tid >> 2) * 8, 8192);
                bulk_load(sbase + tid * 8192, &g_xo[((mh * 8 + o_order[tid]) * 8 + g) * 512], 8192, bar_o + (tid >> 2) * 8);
            }
        }
    }
    STAMP(13);

    {
        const uint4* src = &g_xp[cta * 1024 + tid];
        float s0, s1, s2, s3;
        int it = 0;
        bool stale;
        do {
            uint4 v[8];
#pragma unroll
            for (int i = 0; i < 8; i++) v[i] = ld_gpu(src + i * 128);
            s0 = s1 = s2 = s3 = 0.f;
#pragma unroll
            for (int i = 0; i < 8; i++) {
                s0 += __uint_as_float(v[i].x);
                s1 += __uint_as_float(v[i].y);
                s2 += __uint_as_float(v[i].z);
                s3 += __uint_as_float(v[i].w);
            }
            const float all = (s0 + s1) + (s2 + s3);
            stale = all != all;
            if (stale) {
                stale = false;
#pragma unroll
                for (int i = 0; i < 8; i++) stale |= has_empty(v[i]);
            }
            if (++it > kSpinLimit) __trap();
        } while (stale);
        __syncwarp();
        uint32_t* dst = reinterpret_cast<uint32_t*>(out + ((mh * 8 + g) * 8 + g8) * 512 + jl * 64 + warp * 16 + 2 * t4);
        dst[0] = transpose8x8(pack_bf16(s0, s1));
        dst[4] = transpose8x8(pack_bf16(s2, s3));
    }
    STAMP(14);
    STAMP_FLUSH();
    }
}

typedef CUresult (*EncodeFn)(CUtensorMap*, CUtensorMapDataType, cuuint32_t, void*, const cuuint64_t*, const cuuint64_t*,
                             const cuuint32_t*, const cuuint32_t*, CUtensorMapInterleave, CUtensorMapSwizzle,
                             CUtensorMapL2promotion, CUtensorMapFloatOOBfill);

void encode(EncodeFn fn, CUtensorMap* m, void* base, int rank, const cuuint64_t* dims, const cuuint64_t* strides,
            const cuuint32_t* box, CUtensorMapL2promotion promo = CU_TENSOR_MAP_L2_PROMOTION_L2_256B) {
    const cuuint32_t ones[5] = {1, 1, 1, 1, 1};
    fn(m, CU_TENSOR_MAP_DATA_TYPE_BFLOAT16, rank, base, dims, strides, box, ones, CU_TENSOR_MAP_INTERLEAVE_NONE,
       CU_TENSOR_MAP_SWIZZLE_128B, promo, CU_TENSOR_MAP_FLOAT_OOB_FILL_NONE);
}

}

extern "C" void kernel_launch(void* const* d_in, const int* in_sizes, int n_in, void* d_out, int out_size) {
    (void)in_sizes; (void)n_in; (void)out_size;
    static EncodeFn fn = nullptr;
    if (!fn) {
        void* p = nullptr;
        cudaDriverEntryPointQueryResult q;
        cudaGetDriverEntryPoint("cuTensorMapEncodeTiled", &p, cudaEnableDefault, &q);
        fn = (EncodeFn)p;
        cudaFuncSetAttribute(gqa_fused_kernel, cudaFuncAttributeMaxDynamicSharedMemorySize, SMEM_BYTES);
    }
    CUtensorMap mx, mwq, mk, mv, mwo;
    {
        const cuuint64_t dims[3] = {64, 128, 8}, strides[2] = {1024, 128};
        const cuuint32_t box[3] = {64, 64, XCH / 64};
        encode(fn, &mx, d_in[0], 3, dims, strides, box);
    }
    {
        const cuuint64_t dims[4] = {64, 8, 2, 128 * kSk / 8}, strides[3] = {256, 128, 2048};
        const cuuint32_t box[4] = {64, 8, 2, T / 8};
        encode(fn, &mk, d_in[1], 4, dims, strides, box);
        encode(fn, &mv, d_in[2], 4, dims, strides, box);
    }
    {
        const cuuint64_t dims[2] = {4096, 512}, strides[1] = {8192};
        const cuuint32_t box[2] = {64, 128};
        encode(fn, &mwq, d_in[3], 2, dims, strides, box, WPROMO);
    }
    {
        const cuuint64_t dims[2] = {512, 4096}, strides[1] = {1024};
        const cuuint32_t box[2] = {64, 128};
        encode(fn, &mwo, d_in[4], 2, dims, strides, box, WPROMO);
    }
    gqa_fused_kernel<<<128, 384, SMEM_BYTES>>>(mx, mwq, mk, mv, mwo, (__nv_bfloat16*)d_out);
}
```

```cpp
#include <cuda_runtime.h>
#include <cuda.h>
#include <cuda_bf16.h>
#include <stdint.h>

namespace {

constexpr int kSk = 4096;
constexpr int T = 128;
constexpr int SLOT = T * 256;
constexpr int NS = 4;
constexpr int NT = kSk / T;
constexpr int NKV = 2 * NT;

constexpr int kWindow4 = 12;
constexpr int kWoEarly4 = 4 * NT;
constexpr int kWoLate4 = 4 * NKV - 8;

constexpr int kResetAt = 8;
constexpr int kRegSteps = 28;

constexpr uint32_t A_RING = 1024;
constexpr uint32_t A_X = A_RING + 2 * SLOT;
constexpr uint32_t A_W = A_RING + NS * SLOT;
constexpr uint32_t A_Q = A_W + 65536;
constexpr uint32_t A_P = A_Q + 8192;
constexpr uint32_t A_RED = A_P + 16384;
constexpr uint32_t B_FULL = A_RED + 1024, B_EMPTY = B_FULL + 8 * NS, B_X = B_EMPTY + 8 * NS, B_W = B_X + 16;
constexpr uint32_t B_PROJ_DONE = B_W + 32, B_RESET_GO = B_PROJ_DONE + 8, B_RESET_DONE = B_RESET_GO + 8;
constexpr uint32_t B_OBUF = B_RESET_DONE + 8, B_O = B_OBUF + 8;
constexpr uint32_t A_MEAN = B_O + 16, A_OCOUNT = A_MEAN + 4, A_ORDER = A_OCOUNT + 4;
constexpr int SMEM_BYTES = A_ORDER + 8 - A_RING;
static_assert(SMEM_BYTES <= 232448, "shared memory layout");

constexpr uint32_t kEmpty = 0xFFFFFFFFu;
constexpr int kSpinLimit = 1 << 22;

__device__ uint4 g_xq[128 * 512];
__device__ uint4 g_xo[128 * 512];
__device__ uint4 g_xp[128 * 1024];
__device__ unsigned g_sent[128 * 32];
__device__ unsigned g_arrive[2 * 32];
__device__ __align__(128) unsigned g_stream;

__device__ __forceinline__ uint32_t lds32(uint32_t a) {
    uint32_t v;
    asm volatile("ld.volatile.shared.u32 %0, [%1];" : "=r"(v) : "r"(a) : "memory");
    return v;
}
__device__ __forceinline__ void sts32(uint32_t a, uint32_t v) { asm volatile("st.volatile.shared.u32 [%0], %1;" ::"r"(a), "r"(v) : "memory"); }
__device__ __forceinline__ uint4 lds128(uint32_t a) {
    uint4 v;
    asm volatile("ld.shared.v4.u32 {%0,%1,%2,%3}, [%4];" : "=r"(v.x), "=r"(v.y), "=r"(v.z), "=r"(v.w) : "r"(a) : "memory");
    return v;
}
__device__ __forceinline__ float4 lds128f(uint32_t a) {
    float4 v;
    asm volatile("ld.shared.v4.f32 {%0,%1,%2,%3}, [%4];" : "=f"(v.x), "=f"(v.y), "=f"(v.z), "=f"(v.w) : "r"(a) : "memory");
    return v;
}
__device__ __forceinline__ void sts128(uint32_t a, uint4 v) {
    asm volatile("st.shared.v4.u32 [%0], {%1,%2,%3,%4};" ::"r"(a), "r"(v.x), "r"(v.y), "r"(v.z), "r"(v.w) : "memory");
}
__device__ __forceinline__ void stsm_t(uint32_t a, const uint32_t* r) {
    asm volatile("stmatrix.sync.aligned.m8n8.x4.trans.shared.b16 [%0], {%1,%2,%3,%4};"
                 ::"r"(a), "r"(r[0]), "r"(r[1]), "r"(r[2]), "r"(r[3]) : "memory");
}
__device__ __forceinline__ void ldsm_t(uint32_t (&r)[4], uint32_t a) {
    asm volatile("ldmatrix.sync.aligned.m8n8.x4.trans.shared.b16 {%0,%1,%2,%3}, [%4];"
                 : "=r"(r[0]), "=r"(r[1]), "=r"(r[2]), "=r"(r[3]) : "r"(a) : "memory");
}

__device__ __forceinline__ void mbar_init(uint32_t bar, uint32_t cnt) {
    asm volatile("mbarrier.init.shared::cta.b64 [%0], %1;" ::"r"(bar), "r"(cnt) : "memory");
}
__device__ __forceinline__ void mbar_expect_tx(uint32_t bar, uint32_t bytes) {
    asm volatile("mbarrier.arrive.expect_tx.shared::cta.b64 _, [%0], %1;" ::"r"(bar), "r"(bytes) : "memory");
}
__device__ __forceinline__ void mbar_arrive(uint32_t bar) {
    asm volatile("mbarrier.arrive.shared::cta.b64 _, [%0];" ::"r"(bar) : "memory");
}
__device__ __forceinline__ void mbar_wait(uint32_t bar, uint32_t parity) {
    uint32_t ok;
    int it = 0;
    do {
        asm volatile("{\n.reg .pred p;\nmbarrier.try_wait.parity.shared::cta.b64 p, [%1], %2;\nselp.u32 %0, 1, 0, p;\n}"
                     : "=r"(ok) : "r"(bar), "r"(parity) : "memory");
        if (++it > kSpinLimit) __trap();
    } while (!ok);
}
__device__ __forceinline__ bool mbar_test(uint32_t bar, uint32_t parity) {
    uint32_t ok;
    asm volatile("{\n.reg .pred p;\nmbarrier.test_wait.parity.shared::cta.b64 p, [%1], %2;\nselp.u32 %0, 1, 0, p;\n}"
                 : "=r"(ok) : "r"(bar), "r"(parity) : "memory");
    return ok != 0;
}
__device__ __forceinline__ void wg_bar() { asm volatile("bar.sync 1, 128;" ::: "memory"); }
__device__ __forceinline__ bool wg_any(bool v) {
    uint32_t r;
    asm volatile("{\n.reg .pred p, q;\nsetp.ne.u32 p, %1, 0;\nbar.red.or.pred q, 2, 128, p;\nselp.u32 %0, 1, 0, q;\n}"
                 : "=r"(r) : "r"((uint32_t)v) : "memory");
    return r != 0;
}
__device__ __forceinline__ void fence_async_smem() { asm volatile("fence.proxy.async.shared::cta;" ::: "memory"); }

__device__ __forceinline__ void tma_2d(uint32_t dst, const CUtensorMap* m, uint32_t bar, int c0, int c1) {
    asm volatile("cp.async.bulk.tensor.2d.shared::cluster.global.mbarrier::complete_tx::bytes [%0], [%1, {%3, %4}], [%2];"
                 ::"r"(dst), "l"(m), "r"(bar), "r"(c0), "r"(c1) : "memory");
}
__device__ __forceinline__ void tma_3d(uint32_t dst, const CUtensorMap* m, uint32_t bar, int c0, int c1, int c2) {
    asm volatile("cp.async.bulk.tensor.3d.shared::cluster.global.mbarrier::complete_tx::bytes [%0], [%1, {%3, %4, %5}], [%2];"
                 ::"r"(dst), "l"(m), "r"(bar), "r"(c0), "r"(c1), "r"(c2) : "memory");
}
__device__ __forceinline__ void tma_kv(uint32_t dst, const CUtensorMap* m, uint32_t bar, int group, uint64_t pol) {
    asm volatile("cp.async.bulk.tensor.4d.shared::cluster.global.mbarrier::complete_tx::bytes.L2::cache_hint "
                 "[%0], [%1, {%3, %3, %3, %4}], [%2], %5;"
                 ::"r"(dst), "l"(m), "r"(bar), "r"(0), "r"(group), "l"(pol) : "memory");
}
__device__ __forceinline__ void bulk_load(uint32_t dst, const void* src, uint32_t bytes, uint32_t bar) {
    asm volatile("cp.async.bulk.shared::cluster.global.mbarrier::complete_tx::bytes [%0], [%1], %2, [%3];"
                 ::"r"(dst), "l"(src), "r"(bytes), "r"(bar) : "memory");
}

__host__ __device__ constexpr uint32_t desc_lo(uint32_t addr) { return (addr >> 4) | (1u << 16); }
__host__ __device__ constexpr uint32_t desc_hi(uint32_t sbo) { return (sbo >> 4) | (1u << 30); }
__device__ __forceinline__ void wg_fence() { asm volatile("wgmma.fence.sync.aligned;" ::: "memory"); }
__device__ __forceinline__ void wg_commit() { asm volatile("wgmma.commit_group.sync.aligned;" ::: "memory"); }
__device__ __forceinline__ void wg_wait0() { asm volatile("wgmma.wait_group.sync.aligned 0;" ::: "memory"); }
template <int N>
__device__ __forceinline__ void pin(float (&d)[N]) {
#pragma unroll
    for (int i = 0; i < N; i++) asm volatile("" : "+f"(d[i])::"memory");
}
__device__ __forceinline__ uint32_t uniform(uint32_t v) { return __shfl_sync(~0u, v, 0); }

#define REGS16 "{%0,%1,%2,%3,%4,%5,%6,%7,%8,%9,%10,%11,%12,%13,%14,%15}"
#define REGS32 "{%0,%1,%2,%3,%4,%5,%6,%7,%8,%9,%10,%11,%12,%13,%14,%15,%16,%17,%18,%19,%20,%21,%22,%23,%24,%25,%26,%27,%28,%29,%30,%31}"
#define OPS8(c, d, o) c(d[o]), c(d[o + 1]), c(d[o + 2]), c(d[o + 3]), c(d[o + 4]), c(d[o + 5]), c(d[o + 6]), c(d[o + 7])
#define OPS16(c, d) OPS8(c, d, 0), OPS8(c, d, 8)
#define OPS32(c, d) OPS8(c, d, 0), OPS8(c, d, 8), OPS8(c, d, 16), OPS8(c, d, 24)
#define MMA_N32_SS(c, acc)                                                                                            \
    asm volatile("{\n.reg .b64 da, db;\nmov.b64 da, {%16, %19};\nmov.b64 db, {%17, %20};\n"                           \
                 "wgmma.mma_async.sync.aligned.m64n32k16.f32.bf16.bf16 " REGS16 ", da, db, " acc ", 1, 1, %18, 0;\n}" \
                 : OPS16(c, d) : "r"(a), "r"(b), "n"(TA), "n"(desc_hi(SBO_A)), "n"(desc_hi(SBO_B)))
#define MMA_N32_RS(c, acc)                                                                                            \
    asm volatile("{\n.reg .b64 db;\nmov.b64 db, {%20, %21};\n"                                                        \
                 "wgmma.mma_async.sync.aligned.m64n32k16.f32.bf16.bf16 " REGS16 ", {%16,%17,%18,%19}, db, " acc       \
                 ", 1, 1, 0;\n}"                                                                                      \
                 : OPS16(c, d) : "r"(a[0]), "r"(a[1]), "r"(a[2]), "r"(a[3]), "r"(b), "n"(desc_hi(8192)))
#define MMA_N64_SS(c, acc)                                                                                            \
    asm volatile("{\n.reg .b64 da, db;\nmov.b64 da, {%32, %34};\nmov.b64 db, {%33, %34};\n"                           \
                 "wgmma.mma_async.sync.aligned.m64n64k16.f32.bf16.bf16 " REGS32 ", da, db, " acc ", 1, 1, 0, 1;\n}"   \
                 : OPS32(c, d) : "r"(a), "r"(b), "n"(desc_hi(1024)))

template <int TA, int SBO_A = 2048, int SBO_B = 1024>
__device__ __forceinline__ void mma_n32_ss(float (&d)[16], uint32_t a, uint32_t b, bool first) {
    if (first) MMA_N32_SS("=f", "0");
    else MMA_N32_SS("+f", "1");
}
__device__ __forceinline__ void mma_n32_rs(float (&d)[16], const uint32_t (&a)[4], uint32_t b, bool first) {
    if (first) MMA_N32_RS("=f", "0");
    else MMA_N32_RS("+f", "1");
}
__device__ __forceinline__ void mma_n64_ss(float (&d)[32], uint32_t a, uint32_t b, bool first) {
    if (first) MMA_N64_SS("=f", "0");
    else MMA_N64_SS("+f", "1");
}

__device__ __forceinline__ uint32_t pack_bf16(float lo, float hi) {
    uint32_t r;
    asm("cvt.rn.bf16x2.f32 %0, %1, %2;" : "=r"(r) : "f"(hi), "f"(lo));
    return r;
}
__device__ __forceinline__ float ex2(float x) {
    float r;
    asm("ex2.approx.ftz.f32 %0, %1;" : "=f"(r) : "f"(x));
    return r;
}
__device__ __forceinline__ float rcp(float x) {
    float r;
    asm("rcp.approx.ftz.f32 %0, %1;" : "=f"(r) : "f"(x));
    return r;
}
__device__ __forceinline__ uint32_t transpose8x8(uint32_t a) {
    uint32_t d;
    asm volatile("movmatrix.sync.aligned.m8n8.trans.b16 %0, %1;" : "=r"(d) : "r"(a));
    return d;
}
template <bool IS_MAX>
__device__ __forceinline__ float reduce_scatter8(const float (&v)[8], int lane) {
    auto op = [](float a, float b) { return IS_MAX ? fmaxf(a, b) : a + b; };
    const bool b4 = lane & 16, b3 = lane & 8, b2 = lane & 4;
    float a[4], c[2];
#pragma unroll
    for (int i = 0; i < 4; i++) a[i] = op(b4 ? v[i + 4] : v[i], __shfl_xor_sync(~0u, b4 ? v[i] : v[i + 4], 16));
#pragma unroll
    for (int i = 0; i < 2; i++) c[i] = op(b3 ? a[i + 2] : a[i], __shfl_xor_sync(~0u, b3 ? a[i] : a[i + 2], 8));
    return op(b2 ? c[1] : c[0], __shfl_xor_sync(~0u, b2 ? c[0] : c[1], 4));
}

__device__ __forceinline__ void st_gpu(uint4* p, uint4 v) {
    asm volatile("st.relaxed.gpu.global.v4.u32 [%0], {%1,%2,%3,%4};" ::"l"(p), "r"(v.x), "r"(v.y), "r"(v.z), "r"(v.w) : "memory");
}
__device__ __forceinline__ uint4 ld_gpu(const uint4* p) {
    uint4 v;
    asm volatile("ld.relaxed.gpu.global.v4.u32 {%0,%1,%2,%3}, [%4];" : "=r"(v.x), "=r"(v.y), "=r"(v.z), "=r"(v.w) : "l"(p) : "memory");
    return v;
}
__device__ __forceinline__ uint32_t ld_gpu(const uint32_t* p) {
    uint32_t v;
    asm volatile("ld.relaxed.gpu.global.u32 %0, [%1];" : "=r"(v) : "l"(p) : "memory");
    return v;
}
__device__ __forceinline__ void red_gpu(unsigned* p) { asm volatile("red.relaxed.gpu.global.add.u32 [%0], 1;" ::"l"(p) : "memory"); }
__device__ __forceinline__ void st_gpu_if(bool on, uint4* p, uint4 v) {
    asm volatile("{\n.reg .pred q;\nsetp.ne.u32 q, %5, 0;\n@q st.relaxed.gpu.global.v4.u32 [%0], {%1,%2,%3,%4};\n}"
                 ::"l"(p), "r"(v.x), "r"(v.y), "r"(v.z), "r"(v.w), "r"((uint32_t)on) : "memory");
}
__device__ __forceinline__ void st_gpu_if(bool on, uint32_t* p, uint32_t v) {
    asm volatile("{\n.reg .pred q;\nsetp.ne.u32 q, %2, 0;\n@q st.relaxed.gpu.global.u32 [%0], %1;\n}"
                 ::"l"(p), "r"(v), "r"((uint32_t)on) : "memory");
}
__device__ __forceinline__ void red_gpu_if(bool on, unsigned* p) {
    asm volatile("{\n.reg .pred q;\nsetp.ne.u32 q, %1, 0;\n@q red.relaxed.gpu.global.add.u32 [%0], 1;\n}" ::"l"(p), "r"((uint32_t)on) : "memory");
}
__device__ __forceinline__ void ld_gpu_if(bool on, uint4& v, const uint4* p) {
    asm volatile("{\n.reg .pred q;\nsetp.ne.u32 q, %5, 0;\n@q ld.relaxed.gpu.global.v4.u32 {%0,%1,%2,%3}, [%4];\n}"
                 : "+r"(v.x), "+r"(v.y), "+r"(v.z), "+r"(v.w) : "l"(p), "r"((uint32_t)on) : "memory");
}
__device__ __forceinline__ uint4 as_uint4(const float* v) {
    return make_uint4(__float_as_uint(v[0]), __float_as_uint(v[1]), __float_as_uint(v[2]), __float_as_uint(v[3]));
}
__device__ __forceinline__ bool has_empty(uint4 v) { return v.x == kEmpty || v.y == kEmpty || v.z == kEmpty || v.w == kEmpty; }

__device__ __forceinline__ bool kv_is_k(int i) { return i == 0 || ((i & 1) && i != NKV - 1); }
__device__ __forceinline__ int kv_tile(int i) { return kv_is_k(i) ? (i + 1) >> 1 : (i - 1) >> 1; }

__global__ void __launch_bounds__(384, 1)
gqa_fused_kernel(const __grid_constant__ CUtensorMap map_x, const __grid_constant__ CUtensorMap map_wq,
                 const __grid_constant__ CUtensorMap map_k, const __grid_constant__ CUtensorMap map_v,
                 const __grid_constant__ CUtensorMap map_wo, __nv_bfloat16* __restrict__ out) {
    extern __shared__ __align__(1024) uint8_t smem[];
    const int tid = threadIdx.x, warp = tid >> 5, lane = tid & 31;
    const int cta = blockIdx.x, b = cta >> 3, g = cta & 7, mh = b >> 3, jl = b & 7;

    uint64_t pol = 0;
    if (tid == 128) {
        if ((uint32_t)__cvta_generic_to_shared(smem) != A_RING) __trap();
        mbar_init(B_W, 1);
        fence_async_smem();
        mbar_expect_tx(B_W, 16384);
        tma_2d(A_W, &map_wq, B_W, (g * 8 + jl) * 64, 0);
#pragma unroll
        for (int i = 1; i < 4; i++) mbar_init(B_W + i * 8, 1);
#pragma unroll
        for (int i = 0; i < 2; i++) mbar_init(B_X + i * 8, 1);
#pragma unroll
        for (int i = 0; i < NS; i++) mbar_init(B_FULL + i * 8, 1);
        fence_async_smem();
#pragma unroll
        for (int c = 0; c < 4; c++) {
            if (c > 0) {
                mbar_expect_tx(B_W + c * 8, 16384);
                tma_2d(A_W + c * 16384, &map_wq, B_W + c * 8, (g * 8 + jl) * 64, c * 128);
            }
            if (c % 2 == 0) {
                mbar_expect_tx(B_X + c * 4, SLOT);
                tma_3d(A_X + (c / 2) * SLOT, &map_x, B_X + c * 4, 0, mh * 64, c * 2);
            }
        }
        asm volatile("createpolicy.fractional.L2::evict_first.b64 %0, 1.0;" : "=l"(pol));
        mbar_expect_tx(B_FULL, SLOT);
        tma_kv(A_RING, &map_k, B_FULL, (cta * kSk) >> 3, pol);
#pragma unroll
        for (int i = 0; i < NS; i++) mbar_init(B_EMPTY + i * 8, 4);
        mbar_init(B_PROJ_DONE, 4);
        mbar_init(B_RESET_GO, 1);
        mbar_init(B_RESET_DONE, 1);
        mbar_init(B_OBUF, 4);
        mbar_init(B_O, 4);
        mbar_init(B_O + 8, 4);
        sts32(A_MEAN, 0);
        sts32(A_OCOUNT, 0);
        fence_async_smem();
    }
    __syncthreads();

    if (warp >= 4) {
        if (tid == 128) {
            int issued = 1, landed = 0, wo_issued = 0, it = 0;
            while (landed < NKV || wo_issued < 4) {
                const int mean4 = lds32(A_MEAN), slot = issued & 3;
                if (landed < issued && mbar_test(B_FULL + (landed & 3) * 8, (landed >> 2) & 1)) {
                    red_gpu(&g_stream);
                    landed++;
                    it = 0;
                } else if (issued < NKV && issued - landed < (issued == 2 ? 2 : NS) &&
                           (4 * issued < mean4 + kWindow4 || issued == landed) &&
                           mbar_test(issued == 1 ? B_W + 8 : issued < NS ? B_PROJ_DONE : B_EMPTY + slot * 8,
                                     issued < NS ? 0 : ((issued >> 2) & 1) ^ 1)) {
                    mbar_expect_tx(B_FULL + slot * 8, SLOT);
                    tma_kv(A_RING + slot * SLOT, kv_is_k(issued) ? &map_k : &map_v, B_FULL + slot * 8,
                           (cta * kSk + kv_tile(issued) * T) >> 3, pol);
                    issued++;
                } else if (wo_issued < 4 && mean4 >= (wo_issued < 2 ? kWoEarly4 : kWoLate4) && mbar_test(B_PROJ_DONE, 0)) {
                    mbar_expect_tx(B_W + wo_issued * 8, 16384);
                    tma_2d(A_W + wo_issued * 16384, &map_wo, B_W + wo_issued * 8, jl * 64, g * 512 + wo_issued * 128);
                    wo_issued++;
                } else if (++it > kSpinLimit) {
                    __trap();
                }
            }
        } else if (warp == 5) {
            unsigned* ctr = &g_arrive[mh * 32];
            unsigned target = 0;
            if (lane == 0) target = (ld_gpu(ctr) & ~63u) + 64u;
            mbar_wait(B_RESET_GO, 0);
            const uint4 e = make_uint4(kEmpty, kEmpty, kEmpty, kEmpty);
#pragma unroll 1
            for (int i = 0; i < 16; i++) {
                st_gpu(&g_xo[cta * 512 + i * 32 + lane], e);
                __nanosleep(300);
                st_gpu(&g_xp[cta * 1024 + i * 64 + lane], e);
                __nanosleep(300);
                st_gpu(&g_xp[cta * 1024 + i * 64 + 32 + lane], e);
                __nanosleep(300);
                st_gpu(&g_xq[cta * 512 + i * 32 + lane], make_uint4(0, 0, 0, 0));
                __nanosleep(300);
            }
            __syncwarp();
            if (lane == 0) {
                st_gpu_if(true, &g_sent[cta * 32], 0u);
                asm volatile("fence.acq_rel.gpu;" ::: "memory");
                red_gpu(ctr);
                int it = 0;
                while ((int)(ld_gpu(ctr) - target) < 0)
                    if (++it > kSpinLimit) __trap();
                asm volatile("fence.acq_rel.gpu;" ::: "memory");
                mbar_arrive(B_RESET_DONE);
            }
        } else if (tid == 192) {
            unsigned done;
            int it = 0;
            do {
                done = ld_gpu(&g_stream) & 0xFFFF;
                sts32(A_MEAN, done >> 5);
                if (++it > kSpinLimit) __trap();
            } while (done < 32 * kWoLate4);
        }

        __syncwarp();
        if (lane == 0) {
            mbar_wait(B_RESET_DONE, 0);
            mbar_wait(B_OBUF, 0);
            asm volatile("fence.proxy.async.global;" ::: "memory");
            const int lb = (jl + warp - 4) & 7, src_cta = (mh * 8 + lb) * 8 + g;
            int it = 0;
            while (ld_gpu(&g_sent[src_cta * 32]) == 0)
                if (++it > kSpinLimit) __trap();
            unsigned slot;
            asm volatile("atom.relaxed.cta.shared.inc.u32 %0, [%1], 255;" : "=r"(slot) : "r"(A_OCOUNT) : "memory");
            asm volatile("st.volatile.shared.u8 [%0], %1;" ::"r"(A_ORDER + slot), "r"(lb) : "memory");
            mbar_expect_tx(B_O + (slot >> 2) * 8, 8192);
            bulk_load(A_RING + slot * 8192, &g_xo[src_cta * 512], 8192, B_O + (slot >> 2) * 8);
        }
        if (tid == 128) {
            unsigned before;
            asm volatile("atom.relaxed.gpu.global.add.u32 %0, [%1], 0x10000;" : "=r"(before) : "l"(&g_stream) : "memory");
            st_gpu_if(before >> 16 == 127, &g_stream, 0u);
        }
        return;
    }

    const int g8 = lane >> 2, t4 = lane & 3;
    const uint32_t mat_off = ((lane >> 4) * 8 + (lane & 7)) * 128 + (((2 * warp + ((lane >> 3) & 1)) ^ (lane & 7)) << 4);

#pragma unroll 1
    for (int round = 0; round < 2; round++) {
        const bool live = round == 1;
        float o[2][16], inv_l[8];
#pragma unroll
        for (int i = 0; i < 16; i++) o[0][i] = o[1][i] = 0.f;
#pragma unroll
        for (int i = 0; i < 8; i++) inv_l[i] = 0.f;

        if (!live) {
            float acc[32];
#pragma unroll
            for (int c = 0; c < 4; c++) {
                mbar_wait(B_W + c * 8, 0);
                if (c % 2 == 0) mbar_wait(B_X + c * 4, 0);
                wg_fence();
#pragma unroll
                for (int ks = 0; ks < 8; ks++)
                    mma_n64_ss(acc, desc_lo(A_X) + (2 * c + (ks >> 2)) * 512 + (ks & 3) * 2, desc_lo(A_W) + (8 * c + ks) * 128, (c | ks) == 0);
                wg_commit();
            }
            wg_wait0();
            pin(acc);
            if (lane == 0) mbar_arrive(B_PROJ_DONE);
#pragma unroll
            for (int j = 0; j < 8; j++) {
#pragma unroll
                for (int hi = 0; hi < 2; hi++)
                    sts32(A_P + (2 * warp + hi) * 1024 + g8 * 128 + ((j ^ g8) << 4) + t4 * 4, ~pack_bf16(acc[4 * j + 2 * hi], acc[4 * j + 2 * hi + 1]));
            }
            wg_bar();
#pragma unroll
            for (int i = 0; i < 4; i++) {
                const int u = i * 128 + tid;
                st_gpu(&g_xq[((mh * 8 + (u >> 6)) * 8 + g) * 512 + (jl & 1) * 256 + (jl >> 1) * 64 + (u & 63)], lds128(A_P + u * 16));
            }
        } else {
            {
                const uint4* inbox = &g_xq[cta * 512 + tid];
                uint4 v[4];
                int it = 0;
                bool missing;
                do {
                    missing = false;
#pragma unroll
                    for (int i = 0; i < 4; i++) v[i] = ld_gpu(inbox + i * 128);
#pragma unroll
                    for (int i = 0; i < 4; i++) missing |= v[i].x == 0 || v[i].y == 0 || v[i].z == 0 || v[i].w == 0;
                    if (++it > kSpinLimit) __trap();
                } while (missing);
#pragma unroll
                for (int i = 0; i < 4; i++) sts128(A_Q + (i * 128 + tid) * 16, make_uint4(~v[i].x, ~v[i].y, ~v[i].z, ~v[i].w));
                fence_async_smem();
                wg_bar();
            }

            const float kScale = 0.08838834764831845f * 1.4426950408889634f;
            float s[2][16], alpha[8], mc[8], l_run[8];
#pragma unroll
            for (int i = 0; i < 8; i++) { mc[i] = -INFINITY; l_run[i] = 0.f; alpha[i] = 0.f; }
#pragma unroll
            for (int i = 0; i < 16; i++) s[0][i] = s[1][i] = 0.f;
            const uint32_t red_wr = A_RED + ((8 * (g8 >> 1) + 2 * t4 + (g8 & 1)) * 4 + warp) * 4, red_rd = A_RED + t4 * 32;

#pragma unroll 1
            for (int t = 0; t <= NT; t++) {
                const int jk = max(2 * t - 1, 0), jv = min(2 * t, NKV - 1);
                if (t < NT) {
                    const uint32_t k_lo = uniform(desc_lo(A_RING) + (jk & 3) * (SLOT / 16));
                    mbar_wait(B_FULL + (jk & 3) * 8, (jk >> 2) & 1);
                    wg_fence();
#pragma unroll
                    for (int mb = 0; mb < 2; mb++) {
#pragma unroll
                        for (int ks = 0; ks < 8; ks++)
                            mma_n32_ss<0>(s[mb], k_lo + mb * 1024 + (ks >> 2) * 64 + (ks & 3) * 2,
                                          desc_lo(A_Q) + (ks >> 2) * 256 + (ks & 3) * 2, ks == 0);
                    }
                    wg_commit();
                    wg_wait0();
                    pin(s[0]);
                    pin(s[1]);
                    if (lane == 0) mbar_arrive(t == NT - 1 ? B_OBUF : B_EMPTY + (jk & 3) * 8);

                    float mx[8];
#pragma unroll
                    for (int i = 0; i < 8; i++) {
                        const int r = (i >> 1) * 4 + (i & 1);
                        mx[i] = fmaxf(fmaxf(s[0][r], s[0][r + 2]), fmaxf(s[1][r], s[1][r + 2]));
                    }
                    sts32(red_wr, __float_as_uint(reduce_scatter8<true>(mx, lane)));
                    wg_bar();
#pragma unroll
                    for (int i = 0; i < 8; i++) {
                        const float4 v = lds128f(red_rd + (8 * (i >> 1) + (i & 1)) * 16);
                        const float m_new = fmaxf(mc[i], fmaxf(fmaxf(v.x, v.y), fmaxf(v.z, v.w)) * kScale);
                        alpha[i] = ex2(mc[i] - m_new);
                        mc[i] = m_new;
                        l_run[i] *= alpha[i];
                    }
#pragma unroll
                    for (int mb = 0; mb < 2; mb++) {
                        uint32_t pk[8];
#pragma unroll
                        for (int j = 0; j < 4; j++) {
#pragma unroll
                            for (int hi = 0; hi < 2; hi++) {
                                const float p0 = ex2(fmaf(s[mb][4 * j + 2 * hi], kScale, -mc[2 * j]));
                                const float p1 = ex2(fmaf(s[mb][4 * j + 2 * hi + 1], kScale, -mc[2 * j + 1]));
                                l_run[2 * j] += p0;
                                l_run[2 * j + 1] += p1;
                                pk[2 * j + hi] = pack_bf16(p0, p1);
                            }
                        }
#pragma unroll
                        for (int jp = 0; jp < 2; jp++) stsm_t(A_P + mat_off + (t & 1) * 8192 + mb * 4096 + jp * 2048, pk + 4 * jp);
                    }
                    if (t == NT - 1) sts32(red_wr + 512, __float_as_uint(reduce_scatter8<false>(l_run, lane)));
                    fence_async_smem();
                } else {
#pragma unroll
                    for (int i = 0; i < 8; i++) {
                        const float4 v = lds128f(red_rd + 512 + (8 * (i >> 1) + (i & 1)) * 16);
                        inv_l[i] = rcp((v.x + v.y) + (v.z + v.w));
                    }
                }
                if (t > 0) {
                    const uint32_t v_lo = uniform(desc_lo(A_RING) + (jv & 3) * (SLOT / 16));
                    const uint32_t p_lo = uniform(desc_lo(A_P) + ((t - 1) & 1) * 512);
                    mbar_wait(B_FULL + (jv & 3) * 8, (jv >> 2) & 1);
                    wg_fence();
#pragma unroll
                    for (int ks = 0; ks < 8; ks++) {
#pragma unroll
                        for (int mb = 0; mb < 2; mb++)
                            mma_n32_ss<1>(o[mb], v_lo + ks * 256 + mb * 64, p_lo + (ks >> 2) * 256 + (ks & 3) * 2, false);
                    }
                    wg_commit();
                }
                wg_wait0();
                pin(o[0]);
                pin(o[1]);
                if (t == NT) break;
                if (t > 0 && lane == 0) mbar_arrive(B_EMPTY + (jv & 3) * 8);
#pragma unroll
                for (int mb = 0; mb < 2; mb++) {
#pragma unroll
                    for (int i = 0; i < 16; i++) o[mb][i] *= alpha[(i >> 2) * 2 + (i & 1)];
                }
                wg_bar();
                if (t == kResetAt && tid == 0) mbar_arrive(B_RESET_GO);
                if (t == NT - 2) mbar_wait(B_RESET_DONE, 0);
            }
        }

        {
            const uint32_t st = A_Q + warp * 2048 + (lane & 7) * 128;
#pragma unroll
            for (int r = 0; r < 4; r++) {
                uint32_t pk[4];
#pragma unroll
                for (int i = 0; i < 4; i++)
                    pk[i] = pack_bf16(o[i >> 1][4 * r + 2 * (i & 1)] * inv_l[2 * r], o[i >> 1][4 * r + 2 * (i & 1) + 1] * inv_l[2 * r + 1]);
                stsm_t(st + (r >> 1) * 1024 + ((((r & 1) * 4 + (lane >> 3)) ^ (lane & 7)) << 4), pk);
            }
            __syncwarp();
            uint4 img[4];
#pragma unroll
            for (int i = 0; i < 4; i++) img[i] = lds128(A_Q + (warp * 128 + i * 32 + lane) * 16);
#pragma unroll
            for (int i = 0; i < 4; i++) st_gpu_if(live, &g_xo[cta * 512 + warp * 128 + i * 32 + lane], img[i]);
            red_gpu_if(live && tid == 0, &g_sent[cta * 32]);
        }

        uint32_t wf[kRegSteps][4];
#pragma unroll
        for (int ks = 0; ks < 32; ks++) {
            if (ks % 8 == 0 && live) mbar_wait(B_W + ks, 1);
            const int step = 8 * (ks & 3) + (ks >> 2);
            if (step < kRegSteps) ldsm_t(wf[step % kRegSteps], A_W + mat_off + ks * 2048);
        }
        const uint4* inbox = &g_xp[cta * 1024 + tid];
        uint4 v[8];
#pragma unroll 1
        for (int tries = 0;; tries++) {
            bool suspect = false;
            float acc[2][16];
            uint4* dst[2][4];
            auto product = [&](int quad, bool wait) {
                if (wait) mbar_wait(B_O + quad * 8, tries & 1);
                wg_fence();
#pragma unroll
                for (int step = 0; step < 32; step++) {
                    const uint32_t img = desc_lo(A_RING) + quad * 2048 + (step >> 2) * 64 + (step & 3) * 2;
                    if (step < kRegSteps) mma_n32_rs(acc[quad], wf[step % kRegSteps], img, step == 0);
                    else mma_n32_ss<1, 1024, 8192>(acc[quad], desc_lo(A_W) + (4 * (step & 7) + (step >> 3)) * 128, img, false);
                }
                wg_commit();
                const uint32_t order = lds32(A_ORDER + quad * 4);
#pragma unroll
                for (int j = 0; j < 4; j++) {
                    dst[quad][j] = &g_xp[(b * 8 + ((order >> (8 * j)) & 7)) * 1024 + g * 128 + tid];
                    asm volatile("" : "+l"(dst[quad][j]));
                }
            };
            auto send = [&](int quad) {
                pin(acc[quad]);
                bool bad = false;
#pragma unroll
                for (int j = 0; j < 4; j++) bad |= acc[quad][4 * j] != acc[quad][4 * j] || acc[quad][4 * j + 1] != acc[quad][4 * j + 1];
                bad &= live;
                if (tries > 0 && __any_sync(~0u, bad)) {
                    bool hole = false;
#pragma unroll 1
                    for (int i = lane; i < 2048; i += 32) hole |= has_empty(lds128(A_RING + (quad * 2048 + i) * 16));
                    bad &= __any_sync(~0u, hole);
                }
                suspect |= bad;
#pragma unroll
                for (int j = 0; j < 4; j++) st_gpu_if(live && !bad, dst[quad][j], as_uint4(acc[quad] + 4 * j));
            };
            product(0, live);
            wg_wait0();
            const bool pending = live && !mbar_test(B_O + 8, tries & 1);
            send(0);
            product(1, pending);
            pin(acc[0]);
            wg_wait0();
            send(1);
#pragma unroll
            for (int i = 0; i < 8; i++) {
                v[i] = make_uint4(0, 0, 0, 0);
                ld_gpu_if(live, v[i], inbox + i * 128);
            }
            if (!wg_any(suspect)) break;
            if (tries > kSpinLimit) __trap();
            if (tid < 8) {
                const int lb = (lds32(A_ORDER + (tid & 4)) >> (8 * (tid & 3))) & 7;
                fence_async_smem();
                mbar_expect_tx(B_O + (tid >> 2) * 8, 8192);
                bulk_load(A_RING + tid * 8192, &g_xo[((mh * 8 + lb) * 8 + g) * 512], 8192, B_O + (tid >> 2) * 8);
            }
        }

        float s0, s1, s2, s3;
#pragma unroll 1
        for (int it = 0;; it++) {
            s0 = s1 = s2 = s3 = 0.f;
#pragma unroll
            for (int i = 0; i < 8; i++) {
                s0 += __uint_as_float(v[i].x);
                s1 += __uint_as_float(v[i].y);
                s2 += __uint_as_float(v[i].z);
                s3 += __uint_as_float(v[i].w);
            }
            const float all = (s0 + s1) + (s2 + s3);
            if (live ? all == all : it > 0) break;
            bool hole = !live;
#pragma unroll
            for (int i = 0; i < 8; i++) {
                const bool h = has_empty(v[i]);
                hole |= h;
                ld_gpu_if(h && live, v[i], inbox + i * 128);
            }
            if (!hole) break;
            if (it > kSpinLimit) __trap();
        }
        __syncwarp();
        uint32_t* dst = reinterpret_cast<uint32_t*>(out + ((mh * 8 + g) * 8 + g8) * 512 + jl * 64 + warp * 16 + 2 * t4);
        st_gpu_if(live, dst, transpose8x8(pack_bf16(s0, s1)));
        st_gpu_if(live, dst + 4, transpose8x8(pack_bf16(s2, s3)));
    }
}

typedef CUresult (*EncodeFn)(CUtensorMap*, CUtensorMapDataType, cuuint32_t, void*, const cuuint64_t*, const cuuint64_t*,
                             const cuuint32_t*, const cuuint32_t*, CUtensorMapInterleave, CUtensorMapSwizzle,
                             CUtensorMapL2promotion, CUtensorMapFloatOOBfill);

void encode(EncodeFn fn, CUtensorMap* m, void* base, int rank, const cuuint64_t* dims, const cuuint64_t* strides,
            const cuuint32_t* box, CUtensorMapL2promotion promo) {
    const cuuint32_t ones[5] = {1, 1, 1, 1, 1};
    fn(m, CU_TENSOR_MAP_DATA_TYPE_BFLOAT16, rank, base, dims, strides, box, ones, CU_TENSOR_MAP_INTERLEAVE_NONE,
       CU_TENSOR_MAP_SWIZZLE_128B, promo, CU_TENSOR_MAP_FLOAT_OOB_FILL_NONE);
}

}

extern "C" void kernel_launch(void* const* d_in, const int* in_sizes, int n_in, void* d_out, int out_size) {
    (void)in_sizes; (void)n_in; (void)out_size;
    static EncodeFn fn = nullptr;
    if (!fn) {
        void* p = nullptr;
        cudaDriverEntryPointQueryResult q;
        cudaGetDriverEntryPoint("cuTensorMapEncodeTiled", &p, cudaEnableDefault, &q);
        fn = (EncodeFn)p;
        cudaFuncSetAttribute(gqa_fused_kernel, cudaFuncAttributeMaxDynamicSharedMemorySize, SMEM_BYTES);
    }
    CUtensorMap mx, mwq, mk, mv, mwo;
    {
        const cuuint64_t dims[3] = {64, 128, 8}, strides[2] = {1024, 128};
        const cuuint32_t box[3] = {64, 64, 4};
        encode(fn, &mx, d_in[0], 3, dims, strides, box, CU_TENSOR_MAP_L2_PROMOTION_L2_256B);
    }
    {
        const cuuint64_t dims[4] = {64, 8, 2, 128 * kSk / 8}, strides[3] = {256, 128, 2048};
        const cuuint32_t box[4] = {64, 8, 2, T / 8};
        encode(fn, &mk, d_in[1], 4, dims, strides, box, CU_TENSOR_MAP_L2_PROMOTION_L2_256B);
        encode(fn, &mv, d_in[2], 4, dims, strides, box, CU_TENSOR_MAP_L2_PROMOTION_L2_256B);
    }
    {
        const cuuint64_t dims[2] = {4096, 512}, strides[1] = {8192};
        const cuuint32_t box[2] = {64, 128};
        encode(fn, &mwq, d_in[3], 2, dims, strides, box, CU_TENSOR_MAP_L2_PROMOTION_L2_128B);
    }
    {
        const cuuint64_t dims[2] = {512, 4096}, strides[1] = {1024};
        const cuuint32_t box[2] = {64, 128};
        encode(fn, &mwo, d_in[4], 2, dims, strides, box, CU_TENSOR_MAP_L2_PROMOTION_L2_128B);
    }
    cudaLaunchConfig_t cfg = {};
    cfg.gridDim = dim3(128);
    cfg.blockDim = dim3(384);
    cfg.dynamicSmemBytes = SMEM_BYTES;
    cfg.stream = cudaStreamPerThread;
    cudaLaunchAttribute attr;
    attr.id = cudaLaunchAttributeCooperative;
    attr.val.cooperative = 1;
    cfg.attrs = &attr;
    cfg.numAttrs = 1;
    cudaLaunchKernelEx(&cfg, gqa_fused_kernel, mx, mwq, mk, mv, mwo, (__nv_bfloat16*)d_out);
}
```
